```python
import torch

def _softmax(x, axis=-1):
    return torch.softmax(x, dim=axis)

def _gelu(x):
    return torch.nn.functional.gelu(x, approximate='tanh')

def _silu(x):
    return torch.nn.functional.silu(x)

def _sigmoid(x):
    return torch.sigmoid(x)

def _layernorm(x, axis=-1, eps=1e-05):
    m = x.mean(dim=axis, keepdim=True)
    v = x.var(dim=axis, keepdim=True, unbiased=False)
    return (x - m) / torch.sqrt(v + eps)

def _scatter_add(tgt, idx, src, axis=0):
    return tgt.clone().index_add_(axis, idx, src)

def _segment_sum(src, seg, n):
    out = torch.zeros((n,) + src.shape[1:], dtype=src.dtype)
    return out.index_add_(0, seg, src)

def _pad(x, pw):
    flat = tuple((v for pair in reversed(pw) for v in pair))
    return torch.nn.functional.pad(x, flat)
kernel_name = 'adaLN_cond__mha_block_cached__dense_activation_relu__decode'

def setup_inputs():

    _w = lambda a: (lambda t: t.to(torch.bfloat16) if t.is_floating_point() else t)(torch.as_tensor(a))

    def _A_setup():
        B, Sq, D = (2, 1, 576)
        H, Sk, Dh = (32, 16384, 128)
        return {'x': _w((lambda *s: torch.randn(*s, dtype=torch.bfloat16) * 0.1)(B, Sq, D)), 'k_cache': _w((lambda *s: torch.randn(*s, dtype=torch.bfloat16) * 0.8)(B, H, Sk, Dh)), 'v_cache': _w((lambda *s: torch.randn(*s, dtype=torch.bfloat16) * 1.6)(B, H, Sk, Dh)), 'wq': _w((lambda *s: torch.randn(*s, dtype=torch.bfloat16) * 0.8)(D, H * Dh) * D ** (-0.5)), 'wo': _w((lambda *s: torch.randn(*s, dtype=torch.bfloat16) * 1.6)(H * Dh, D) * (H * Dh) ** (-0.5))}
    _A_in = _A_setup()

    def _B_setup():
        B, S, D, Dff = (2, 1, 576, 4608)
        return {'x': _w((lambda *s: torch.randn(*s, dtype=torch.bfloat16) * 0.1)(B, S, D)), 'w1': _w((lambda *s: torch.randn(*s, dtype=torch.bfloat16) * 0.1)(D, Dff)), 'w2': _w((lambda *s: torch.randn(*s, dtype=torch.bfloat16) * 0.1)(Dff, D))}
    _B_in = _B_setup()
    return {'A_x': _A_in['x'], 'A_k_cache': _A_in['k_cache'], 'A_v_cache': _A_in['v_cache'], 'A_wq': _A_in['wq'], 'A_wo': _A_in['wo'], 'B_x': _B_in['x'], 'B_w1': _B_in['w1'], 'B_w2': _B_in['w2'], 'c': _w((lambda *s: torch.randn(*s, dtype=torch.bfloat16) * 0.2)(2, 576) * 8.0), 'w_mod': _w((lambda *s: torch.randn(*s, dtype=torch.bfloat16) * 0.2)(576, 6 * 576) * 576 ** (-0.5) * 8.0)}

def reference(A_x, A_k_cache, A_v_cache, A_wq, A_wo, B_x, B_w1, B_w2, c, w_mod):

    def _A_ref(x, k_cache, v_cache, wq, wo):
        B, Sq, D = x.shape
        H, Dh = (32, 128)
        q = (lambda x, *d: x.permute(*d))((x @ wq).reshape(B, Sq, H, Dh), 0, 2, 1, 3)
        scores = torch.einsum('bhqd,bhkd->bhqk', q, k_cache) * Dh ** (-0.5)
        p = _softmax(scores, axis=-1)
        o = torch.einsum('bhqk,bhkd->bhqd', p, v_cache)
        return (lambda x, *d: x.permute(*d))(o, 0, 2, 1, 3).reshape(B, Sq, H * Dh) @ wo

    def _B_ref(x, w1, w2):
        h = torch.einsum('bsd,df->bsf', x, w1)
        zero = torch.zeros_like(h)
        h = torch.maximum(h, zero)
        return torch.einsum('bsf,fd->bsd', h, w2)
    x = A_x
    mod = (_silu(c) @ w_mod).reshape(c.shape[0], 6, 1, -1)
    sa, ca, ga, sb, cb, gb = (mod[:, 0].clone(), mod[:, 1].clone(), mod[:, 2].clone(), mod[:, 3].clone(), mod[:, 4].clone(), mod[:, 5].clone())
    h = _layernorm(x, axis=-1) * (1 + ca) + sa
    x = x + ga * _A_ref(h, A_k_cache, A_v_cache, A_wq, A_wo)
    h = _layernorm(x, axis=-1) * (1 + cb) + sb
    x = x + gb * _B_ref(h, B_w1, B_w2)
    return x
```

```cpp
#include <cuda_runtime.h>
#include <cuda_bf16.h>
#include <cuda.h>
#include <stdint.h>

namespace {

constexpr int kD = 576, kSk = 16384, kDh = 128, kDff = 4608, kMod = 3456, kHD = 4096;
constexpr int kCtas = 128;
constexpr int kThreads = 384;
constexpr int kTileBytes = 16384;
constexpr int kSlots = 12;
constexpr int kPairs = 128;
constexpr int kWPitch = 1152;
constexpr int kW1Pitch = 80;
constexpr int kModCtas = 108;
constexpr int kHPitch = 592;

constexpr int kWinMid = 4, kWinMin = 3, kWinMax = 11;
constexpr int kWinBias = 128;
constexpr int kTrimFrom = 384, kTrimShift = 5, kTrimDecay = 4, kTrimMax = 160, kFarAhead = 12;
constexpr int kSwitch = 114;
constexpr int kTotal = kCtas * (2 * kPairs - 12);
constexpr int kFfHold = 400;
constexpr int kFfWin = 3, kFfWinLate = 6, kFfLate = 700;
constexpr int kProbes = 4;
constexpr unsigned kProbeDelay = 200, kProbeLimit = 6500;
constexpr unsigned kLastPollDelay = 400;

constexpr int SM_RING = 0;
constexpr int SM_W = SM_RING + 108 * 1024;
constexpr int SM_M = SM_W + 64 * kWPitch;
constexpr int SM_W1 = SM_RING + 8 * kTileBytes;
constexpr int SM_W2 = SM_W1 + 576 * kW1Pitch;
constexpr int SM_TMP = SM_RING + kSlots * kTileBytes;
constexpr int SM_BAR = SM_W2 + 40 * kWPitch;
constexpr int SM_RED = SM_BAR + 352;
constexpr int SM_Q = SM_RED + 2560;
constexpr int SM_H2 = SM_Q + 256;
constexpr int SM_OB = SM_H2;
constexpr int SM_COMB = SM_OB + 256;
constexpr int SM_CM = SM_COMB + 16 * 66 * 4;
constexpr int SM_CL = SM_CM + 64;
constexpr int SM_LN = SM_CL + 64;
constexpr int SM_H1 = SM_LN + 64;
constexpr int SM_FLAG = SM_H1 + 192;
constexpr int SM_TOTAL = SM_FLAG + 16;
static_assert(2 * kHPitch * 2 <= 256 + 8 * 66 * 4, "h2 overlay");
static_assert(SM_TMP + 2 * 4 * 576 * 2 <= SM_BAR && SM_M % 512 == 0 && SM_M + 576 * 64 <= SM_BAR, "");
static_assert((kSwitch - 6) % 6 == 0 && kSwitch + 4 < kPairs, "");
static_assert(kWinMid <= 8 && kWinMax <= 12, "a slot must not be reused before its landing was observed");
static_assert(SM_W % 1024 == 0 && SM_W2 % 1024 == 0, "swizzle atom");
static_assert(SM_TOTAL <= 232448, "smem");

constexpr int BAR_FULL = 0, BAR_EMPTY = 12, BAR_WO = 24, BAR_WFREE = 25, BAR_Q = 26, BAR_COMB = 27, BAR_M = 28,
              BAR_WQ = 29  , BAR_FF = 32  , BAR_COUNT = 43;

constexpr int kSpinLimit = 1 << 17;

constexpr int kX1Copies = 8;
struct __align__(8192) Scratch {
    uint4 in3[kCtas * 2 * 256];
    uint4 in1[kCtas * 2 * 256];
    uint4 x1[kX1Copies * 256];
    uint4 mod[2 * 864];
    unsigned pick[3 * kCtas];
    unsigned epoch;
    __align__(128) unsigned progress[2 * 32];
};
__device__ Scratch g_s;

__device__ __forceinline__ float bflo(uint32_t v) { return __uint_as_float(v << 16); }
__device__ __forceinline__ float bfhi(uint32_t v) { return __uint_as_float(v & 0xffff0000u); }
__device__ __forceinline__ uint32_t pack_bf16(float lo, float hi) {
    uint32_t r; asm("cvt.rn.bf16x2.f32 %0, %1, %2;" : "=r"(r) : "f"(hi), "f"(lo)); return r;
}
__device__ __forceinline__ float bf16r(float x) { return __uint_as_float(pack_bf16(0.f, x)); }
__device__ __forceinline__ uint16_t bf16bits(float x) { return (uint16_t)pack_bf16(x, 0.f); }
__device__ __forceinline__ float fsqrt(float x) { float r; asm("sqrt.approx.ftz.f32 %0, %1;" : "=f"(r) : "f"(x)); return r; }
__device__ __forceinline__ float frcp(float x) { float r; asm("rcp.approx.ftz.f32 %0, %1;" : "=f"(r) : "f"(x)); return r; }
template <class T> __device__ __forceinline__ void pin(T*& p) { asm volatile("" : "+l"(p)); }
__device__ __forceinline__ float ex2(float x) { float r; asm("ex2.approx.ftz.f32 %0, %1;" : "=f"(r) : "f"(x)); return r; }

__device__ __forceinline__ void mbar_init(uint32_t bar, uint32_t cnt) {
    asm volatile("mbarrier.init.shared::cta.b64 [%0], %1;" :: "r"(bar), "r"(cnt) : "memory");
}
__device__ __forceinline__ void mbar_expect_tx(uint32_t bar, uint32_t bytes) {
    asm volatile("mbarrier.arrive.expect_tx.shared::cta.b64 _, [%0], %1;" :: "r"(bar), "r"(bytes) : "memory");
}
__device__ __forceinline__ void mbar_arrive(uint32_t bar) {
    asm volatile("mbarrier.arrive.shared::cta.b64 _, [%0];" :: "r"(bar) : "memory");
}
__device__ __forceinline__ bool mbar_try(uint32_t bar, uint32_t parity) {
    uint32_t ok;
    asm volatile("{\n.reg .pred p;\nmbarrier.try_wait.parity.shared::cta.b64 p, [%1], %2;\nselp.u32 %0, 1, 0, p;\n}"
                 : "=r"(ok) : "r"(bar), "r"(parity) : "memory");
    return ok;
}
__device__ __forceinline__ void mbar_wait(uint32_t bar, uint32_t parity, int& budget) {
    while (!mbar_try(bar, parity) && --budget > 0) {}
}
__device__ __forceinline__ void bulk_load(uint32_t dst, const void* src, uint32_t bytes, uint32_t bar, uint64_t pol) {
    asm volatile("cp.async.bulk.shared::cluster.global.mbarrier::complete_tx::bytes.L2::cache_hint [%0], [%1], %2, [%3], %4;"
                 :: "r"(dst), "l"(src), "r"(bytes), "r"(bar), "l"(pol) : "memory");
}
__device__ __forceinline__ void tma_load_2d(uint32_t dst, const CUtensorMap* map, int x, int y, uint32_t bar) {
    asm volatile("cp.async.bulk.tensor.2d.shared::cluster.global.mbarrier::complete_tx::bytes [%0], [%1, {%3, %4}], [%2];"
                 :: "r"(dst), "l"(map), "r"(bar), "r"(x), "r"(y) : "memory");
}
__device__ __forceinline__ void tma_load_rows(uint32_t dst, const CUtensorMap* map, int row, uint32_t bar) {
    asm volatile("cp.async.bulk.tensor.3d.shared::cluster.global.mbarrier::complete_tx::bytes [%0], [%1, {%3, %3, %4}], [%2];"
                 :: "r"(dst), "l"(map), "r"(bar), "r"(0), "r"(row) : "memory");
}
__device__ __forceinline__ void ldsm4(uint32_t (&r)[4], uint32_t a) {
    asm volatile("ldmatrix.sync.aligned.m8n8.x4.shared.b16 {%0,%1,%2,%3}, [%4];"
                 : "=r"(r[0]), "=r"(r[1]), "=r"(r[2]), "=r"(r[3]) : "r"(a) : "memory");
}
__device__ __forceinline__ void ldsm4t(uint32_t (&r)[4], uint32_t a) {
    asm volatile("ldmatrix.sync.aligned.m8n8.x4.trans.shared.b16 {%0,%1,%2,%3}, [%4];"
                 : "=r"(r[0]), "=r"(r[1]), "=r"(r[2]), "=r"(r[3]) : "r"(a) : "memory");
}
__device__ __forceinline__ void ldsm2t(uint32_t (&r)[2], uint32_t a) {
    asm volatile("ldmatrix.sync.aligned.m8n8.x2.trans.shared.b16 {%0,%1}, [%2];"
                 : "=r"(r[0]), "=r"(r[1]) : "r"(a) : "memory");
}
__device__ __forceinline__ void mma16(float (&c)[4], uint32_t a0, uint32_t a1, uint32_t a2, uint32_t a3,
                                      uint32_t b0, uint32_t b1) {
    asm("mma.sync.aligned.m16n8k16.row.col.f32.bf16.bf16.f32 {%0,%1,%2,%3}, {%4,%5,%6,%7}, {%8,%9}, {%0,%1,%2,%3};"
        : "+f"(c[0]), "+f"(c[1]), "+f"(c[2]), "+f"(c[3])
        : "r"(a0), "r"(a1), "r"(a2), "r"(a3), "r"(b0), "r"(b1));
}
__device__ __forceinline__ void mma8(float (&c)[4], uint32_t a0, uint32_t a1, uint32_t b0) {
    asm("mma.sync.aligned.m16n8k8.row.col.f32.bf16.bf16.f32 {%0,%1,%2,%3}, {%4,%5}, {%6}, {%0,%1,%2,%3};"
        : "+f"(c[0]), "+f"(c[1]), "+f"(c[2]), "+f"(c[3]) : "r"(a0), "r"(a1), "r"(b0));
}
__device__ __forceinline__ uint32_t lds32(uint32_t a) { uint32_t v; asm volatile("ld.volatile.shared.u32 %0, [%1];" : "=r"(v) : "r"(a) : "memory"); return v; }
__device__ __forceinline__ float ldsf(uint32_t a) { return __uint_as_float(lds32(a)); }
__device__ __forceinline__ uint2 lds64(uint32_t a) { uint2 v; asm volatile("ld.shared.v2.u32 {%0, %1}, [%2];" : "=r"(v.x), "=r"(v.y) : "r"(a) : "memory"); return v; }
__device__ __forceinline__ uint4 lds128(uint32_t a) {
    uint4 v; asm volatile("ld.shared.v4.u32 {%0, %1, %2, %3}, [%4];" : "=r"(v.x), "=r"(v.y), "=r"(v.z), "=r"(v.w) : "r"(a) : "memory"); return v;
}
__device__ __forceinline__ float4 ldsf4(uint32_t a) {
    const uint4 v = lds128(a); return make_float4(__uint_as_float(v.x), __uint_as_float(v.y), __uint_as_float(v.z), __uint_as_float(v.w));
}
__device__ __forceinline__ void sts16(uint32_t a, uint16_t v) { asm volatile("st.shared.u16 [%0], %1;" :: "r"(a), "h"(v) : "memory"); }
__device__ __forceinline__ void sts32(uint32_t a, uint32_t v) { asm volatile("st.volatile.shared.u32 [%0], %1;" :: "r"(a), "r"(v) : "memory"); }
__device__ __forceinline__ void stsf2(uint32_t a, float x, float y) { asm volatile("st.shared.v2.f32 [%0], {%1, %2};" :: "r"(a), "f"(x), "f"(y) : "memory"); }
__device__ __forceinline__ void pin32(uint32_t& v) { asm volatile("" : "+r"(v)); }
__device__ __forceinline__ void bar_compute() { asm volatile("bar.sync 1, 256;" ::: "memory"); }
__device__ __forceinline__ uint32_t mapa(uint32_t a, uint32_t rank) {
    uint32_t r; asm("mapa.shared::cluster.u32 %0, %1, %2;" : "=r"(r) : "r"(a), "r"(rank)); return r;
}
__device__ __forceinline__ void st_async32(uint32_t a, uint32_t v, uint32_t bar) {
    asm volatile("st.async.weak.shared::cluster.mbarrier::complete_tx::bytes.b32 [%0], %1, [%2];"
                 :: "r"(a), "r"(v), "r"(bar) : "memory");
}
__device__ __forceinline__ void st_async64(uint32_t a, uint32_t v0, uint32_t v1, uint32_t bar) {
    asm volatile("st.async.weak.shared::cluster.mbarrier::complete_tx::bytes.v2.b32 [%0], {%1, %2}, [%3];"
                 :: "r"(a), "r"(v0), "r"(v1), "r"(bar) : "memory");
}
__device__ __forceinline__ void st_word(uint4* p, uint32_t a, uint32_t b, uint32_t c, uint32_t tag) {
    asm volatile("{\n.reg .b128 t;\n.reg .b64 lo, hi;\nmov.b64 lo, {%1, %2};\nmov.b64 hi, {%3, %4};\n"
                 "mov.b128 t, {lo, hi};\nst.relaxed.gpu.global.b128 [%0], t;\n}"
                 :: "l"(p), "r"(a), "r"(b), "r"(c), "r"(tag) : "memory");
}
__device__ __forceinline__ void xchg_word(uint4* p, uint32_t a, uint32_t b, uint32_t c, uint32_t tag) {
    asm volatile("{\n.reg .b128 t, o;\n.reg .b64 lo, hi;\nmov.b64 lo, {%1, %2};\nmov.b64 hi, {%3, %4};\n"
                 "mov.b128 t, {lo, hi};\natom.relaxed.gpu.global.exch.b128 o, [%0], t;\n}"
                 :: "l"(p), "r"(a), "r"(b), "r"(c), "r"(tag) : "memory");
}
__device__ __forceinline__ uint4 ld_word(const uint4* p) {
    uint4 v;
    asm volatile("{\n.reg .b128 t;\n.reg .b64 lo, hi;\nld.relaxed.gpu.global.b128 t, [%4];\n"
                 "mov.b128 {lo, hi}, t;\nmov.b64 {%0, %1}, lo;\nmov.b64 {%2, %3}, hi;\n}"
                 : "=r"(v.x), "=r"(v.y), "=r"(v.z), "=r"(v.w) : "l"(p) : "memory");
    return v;
}
template <bool ATOMIC>
__device__ __forceinline__ void put_f24x5(uint4* p, const float (&v)[5], uint32_t tag8) {
    uint32_t u[5];
#pragma unroll
    for (int i = 0; i < 5; i++) u[i] = __float_as_uint(v[i]);
    const uint32_t a = __byte_perm(u[0], u[1], 0x5321), b = __byte_perm(u[1], u[2], 0x6532);
    const uint32_t c = __byte_perm(u[2], u[3], 0x7653), d = __byte_perm(u[4], tag8, 0x4321);
    if (ATOMIC) xchg_word(p, a, b, c, d); else st_word(p, a, b, c, d);
}
template <int N>
__device__ __forceinline__ void gather_sum(const uint4* p, uint32_t tag8, float (&s)[5], int& budget) {
    uint4 w[N];
#pragma unroll
    for (int k = 0; k < N; k++) w[k] = ld_word(p + k * 32);
    while (true) {
        bool more = false;
#pragma unroll
        for (int k = 0; k < N; k++) more |= (w[k].w >> 24) != tag8;
        if (!__any_sync(~0u, more) || --budget <= 0) break;
#pragma unroll
        for (int k = 0; k < N; k++) if ((w[k].w >> 24) != tag8) w[k] = ld_word(p + k * 32);
    }
    float a[5][N];
#pragma unroll
    for (int k = 0; k < N; k++) {
        a[0][k] = __uint_as_float(w[k].x << 8);
        a[1][k] = __uint_as_float(__byte_perm(w[k].x, w[k].y, 0x5430) & 0xffffff00u);
        a[2][k] = __uint_as_float(__byte_perm(w[k].y, w[k].z, 0x4320) & 0xffffff00u);
        a[3][k] = __uint_as_float(w[k].z & 0xffffff00u);
        a[4][k] = __uint_as_float(w[k].w << 8);
    }
#pragma unroll
    for (int k = N - 1; k > 0; k--) {
#pragma unroll
        for (int i = 0; i < 5; i++) a[i][(k - 1) >> 1] += a[i][k];
    }
#pragma unroll
    for (int o = 2; o < 32; o <<= 1) {
#pragma unroll
        for (int i = 0; i < 5; i++) a[i][0] += __shfl_xor_sync(~0u, a[i][0], o);
    }
#pragma unroll
    for (int i = 0; i < 5; i++) s[i] = a[i][0];
}
__device__ __forceinline__ float ln_mod(float x, float mean_b, float inv_sd, float c1, float s) {
    const float n = bf16r(bf16r(x - mean_b) * inv_sd);
    return bf16r(n * c1) + s;
}

struct Params {
    const __nv_bfloat16 *x, *k, *v, *c;
    __nv_bfloat16* out;
};

__global__ void __cluster_dims__(2, 1, 1) __launch_bounds__(kThreads, 1)
fused_decode_kernel(const __grid_constant__ CUtensorMap wmmap, const __grid_constant__ CUtensorMap wqmap,
                    const __grid_constant__ CUtensorMap womap, const __grid_constant__ CUtensorMap w1map,
                    const __grid_constant__ CUtensorMap w2map, const Params p) {
    extern __shared__ __align__(1024) unsigned char smem[];
    uint32_t sb = (uint32_t)__cvta_generic_to_shared(smem);
    const int tid = threadIdx.x, warp = tid >> 5, lane = tid & 31;
    const int cta = blockIdx.x, cl = cta >> 1, rank = cta & 1;
    const int b = cl >> 5, h = cl & 31;
    auto bar = [&](int i) { return sb + SM_BAR + i * 8; };
    int budget = kSpinLimit;
    const bool do_mod = cta < kModCtas;
    const int ffcol0 = 72 * cl + 40 * rank;

    if (warp < 8) {
        asm volatile("setmaxnreg.inc.sync.aligned.u32 232;");
        pin32(sb);
        asm volatile("barrier.cluster.arrive.relaxed.aligned;" ::: "memory");
        const int g = lane >> 2, t = lane & 3;
        float* const s_red = (float*)(smem + SM_RED);
        uint32_t tag;
        asm volatile("ld.relaxed.gpu.global.u32 %0, [%1];" : "=r"(tag) : "l"(&g_s.epoch) : "memory");

        uint2 c4[2] = {make_uint2(0, 0), make_uint2(0, 0)}, x4 = make_uint2(0, 0);
        if (tid < 144) {
            c4[0] = __ldg((const uint2*)p.c + tid); c4[1] = __ldg((const uint2*)(p.c + kD) + tid);
            x4 = __ldg((const uint2*)(p.x + b * kD) + tid);
        }
        uint32_t xs[9];
#pragma unroll
        for (int i = 0; i < 9; i++) xs[i] = __ldg((const uint32_t*)(p.x + b * kD) + lane + 32 * i);
        const int rcnt = (cta & 32) ? 4 : 5;
        const int rcol = b * kD + ((cta >> 3) & 7) * 16 + (lane & 1) * 8 + (cta & 7);
        float rx[5];
#pragma unroll
        for (int i = 0; i < 5; i++) rx[i] = i < rcnt ? bflo(__ldg((const unsigned short*)p.x + rcol + 128 * i)) : 0.f;
        asm volatile("barrier.cluster.wait.acquire.aligned;" ::: "memory");
        if (do_mod && tid < 16) st_word(&g_s.mod[(tid >> 3) * 864 + cta * 8 + (tid & 7)], 0, 0, 0, 0);
        tag += 1;
        const bool five = warp < 4;
        const int idx4 = five ? warp + 32 : warp;
        const uint32_t koff = sb + SM_RING + ((warp & 3) * 16 + ((lane >> 3) & 1) * 8 + (lane & 7)) * 256 + (((lane >> 4) ^ (lane & 7)) << 4);
        const uint32_t voff = sb + SM_RING + kTileBytes + ((warp & 3) * 16 + (lane >> 4) * 8 + (lane & 7)) * 256 + ((((lane >> 3) & 1) ^ (lane & 7)) << 4);
        const bool odd = g & 1, valid = (t == (g >> 1));
        const float kL2E = 1.4426950408889634f, kScale = 0.08838834764831845f;
        float acc[8][4], m = -3.0e38f, l = 0.f;
        uint32_t wf[5][4][4], qf[16];
#pragma unroll
        for (int j = 0; j < 8; j++) { acc[j][0] = acc[j][1] = acc[j][2] = acc[j][3] = 0.f; }

        const int grp = warp >> 2;
        int slot = 2 * grp;
        uint32_t par = 0;
        auto attend = [&](int n, int nslots) {
#pragma unroll 1
            for (; n > 0; n--) {
                const uint32_t so = slot * kTileBytes;
                mbar_wait(bar(BAR_FULL + slot), par, budget);
                float c0[4] = {0.f, 0.f, 0.f, 0.f}, c1[4] = {0.f, 0.f, 0.f, 0.f};
#pragma unroll
                for (int u = 0; u < 4; u++) {
                    uint32_t a[4], a2[4];
                    const uint32_t ad = (koff + so) ^ (u << 5);
                    ldsm4(a, ad);
                    ldsm4(a2, ad + 128);
                    mma16(c0, a[0], a[1], a[2], a[3], qf[2 * u], qf[2 * u + 1]);
                    mma16(c1, a2[0], a2[1], a2[2], a2[3], qf[2 * u + 8], qf[2 * u + 9]);
                }
                __syncwarp();
                if (lane == 0) mbar_arrive(bar(BAR_EMPTY + slot));
                float s0 = odd ? c0[1] + c1[1] : c0[0] + c1[0];
                float s1 = odd ? c0[3] + c1[3] : c0[2] + c1[2];
                s0 = valid ? bf16r(bf16r(s0) * kScale) : -INFINITY;
                s1 = valid ? bf16r(bf16r(s1) * kScale) : -INFINITY;
                float mx = fmaxf(s0, s1);
                if (__any_sync(~0u, mx > m)) {
#pragma unroll
                    for (int o = 16; o; o >>= 1) mx = fmaxf(mx, __shfl_xor_sync(~0u, mx, o));
                    const float sc = ex2((m - mx) * kL2E);
                    m = mx; l *= sc;
#pragma unroll
                    for (int u = 0; u < 8; u++) { acc[u][0] *= sc; acc[u][1] *= sc; acc[u][2] *= sc; acc[u][3] *= sc; }
                }
                const float p0 = ex2((s0 - m) * kL2E), p1 = ex2((s1 - m) * kL2E);
                float ps = p0 + p1;
#pragma unroll
                for (int o = 16; o; o >>= 1) ps += __shfl_xor_sync(~0u, ps, o);
                l += ps;
                const uint32_t pb0 = odd ? pack_bf16(0.f, p0) : pack_bf16(p0, 0.f);
                const uint32_t pb1 = odd ? pack_bf16(0.f, p1) : pack_bf16(p1, 0.f);
                mbar_wait(bar(BAR_FULL + slot + 1), par, budget);
#pragma unroll
                for (int u = 0; u < 4; u++) {
                    uint32_t a[4], a2[4];
                    const uint32_t ad = (voff + so) ^ (u << 5);
                    ldsm4t(a, ad);
                    ldsm4t(a2, ad + 128);
                    mma16(acc[u], a[0], a[1], a[2], a[3], pb0, pb1);
                    mma16(acc[u + 4], a2[0], a2[1], a2[2], a2[3], pb0, pb1);
                }
                __syncwarp();
                if (lane == 0) mbar_arrive(bar(BAR_EMPTY + slot + 1));
                slot += 4;
                if (slot >= nslots) { slot -= nslots; par ^= 1; }
            }
        };
        auto wtile = [&](int i) {
            const int ci = 2 * (i < 4 ? warp + 8 * i : idx4) + ((lane >> 3) & 1), cb = ci >> 3;
            return (uint32_t)((lane & 7) * kWPitch + cb * 128 + (((ci ^ (lane + cb)) & 7) << 4));
        };
        uint4* p_in1 = &g_s.in1[(b * 64 + warp * 8 + g) * 512 + (cta & 63) * 2 + (t & 1)];
        uint4* p_in3 = &g_s.in3[((t >> 1) * 64 + warp * 8 + g) * 512 + cta * 2 + (t & 1)];
        uint32_t mine = 0;
        uint4* p_x1 = &g_s.x1[((lane >> 1) & (kX1Copies - 1)) * 2 * kCtas + cta * 2 + (lane & 1)];
        const uint4* p_xw = &g_s.x1[(cta & (kX1Copies - 2)) * 256 + tid];
        uint32_t rk = rank;
        uint32_t peer = mapa(sb, rank ^ 1);
        uint32_t a_comb = sb + SM_COMB + (t * 4 * 66 + (tid >> 2)) * 4;
        uint32_t a_h2 = sb + SM_H2 + (grp * kHPitch + ((tid >> 4) & 7) * 16 + ((tid >> 2) & 3) * 4 + (tid & 1) * 2 + ((tid >> 1) & 1)) * 2;
        const int lcol = ((tid >> 4) & 7) * 16 + (tid & 1) * 8 + ((tid >> 1) & 7);
        const int lcnt = (tid & 64) ? 4 : 5;
        uint32_t csb[5] = {0, 0, 0, 0, 0}, rgab[5] = {0, 0, 0, 0, 0};

        if (do_mod) {
            if (tid < 144) {
                auto silu = [](float v) { return __fdividef(v, 1.f + __expf(-v)); };
#pragma unroll
                for (int bb = 0; bb < 2; bb++)
                    *(uint2*)(smem + SM_H2 + bb * kHPitch * 2 + tid * 8) =
                        make_uint2(pack_bf16(silu(bflo(c4[bb].x)), silu(bfhi(c4[bb].x))), pack_bf16(silu(bflo(c4[bb].y)), silu(bfhi(c4[bb].y))));
            }
            bar_compute();
            uint32_t sf[5][2], mf[5][2][4];
            const uint32_t* sp = (const uint32_t*)(smem + SM_H2) + (g & 1) * (kHPitch / 2) + t;
#pragma unroll
            for (int i = 0; i < 5; i++) {
                const int ks = i < 4 ? warp + 8 * i : idx4;
                const bool on = g < 2 && (i < 4 || five);
                sf[i][0] = on ? sp[ks * 8] : 0u; sf[i][1] = on ? sp[ks * 8 + 4] : 0u;
            }
            mbar_wait(bar(BAR_M), 0, budget);
            const uint32_t base = sb + SM_M + ((lane >> 4) * 8 + (lane & 7)) * 64;
#pragma unroll
            for (int i = 0; i < 5; i++) {
#pragma unroll
                for (int mt = 0; mt < 2; mt++)
                    ldsm4t(mf[i][mt], base + (i < 4 ? warp + 8 * i : idx4) * 1024 + (((2 * mt + ((lane >> 3) & 1)) ^ ((lane & 7) >> 1)) << 4));
            }
            float c[2][4] = {{0.f, 0.f, 0.f, 0.f}, {0.f, 0.f, 0.f, 0.f}};
#pragma unroll
            for (int i = 0; i < 5; i++) {
#pragma unroll
                for (int mt = 0; mt < 2; mt++) mma16(c[mt], mf[i][mt][0], mf[i][mt][1], mf[i][mt][2], mf[i][mt][3], sf[i][0], sf[i][1]);
            }
            if (t == 0) {
#pragma unroll
                for (int mt = 0; mt < 2; mt++) {
                    float* rp = s_red + warp * 64 + mt * 16 + g;
                    rp[0] = c[mt][0]; rp[32] = c[mt][1]; rp[8] = c[mt][2]; rp[40] = c[mt][3];
                }
            }
            bar_compute();
            if (tid < 16) {
                float4 s = *(const float4*)(s_red + tid * 4);
#pragma unroll
                for (int w = 1; w < 8; w++) { const float4 v = *(const float4*)(s_red + w * 64 + tid * 4); s.x += v.x; s.y += v.y; s.z += v.z; s.w += v.w; }
                st_word(&g_s.mod[(tid >> 3) * 864 + cta * 8 + (tid & 7)], pack_bf16(s.x, s.y), pack_bf16(s.z, s.w), tag, tag);
            }
        }
        float mean_b, sd_b;
        {
            float s = 0.f;
#pragma unroll
            for (int i = 0; i < 9; i++) s += bflo(xs[i]) + bfhi(xs[i]);
#pragma unroll
            for (int o = 16; o; o >>= 1) s += __shfl_xor_sync(~0u, s, o);
            const float mean = s * (1.f / kD);
            float v = 0.f;
#pragma unroll
            for (int i = 0; i < 9; i++) { const float d0 = bflo(xs[i]) - mean, d1 = bfhi(xs[i]) - mean; v = fmaf(d0, d0, fmaf(d1, d1, v)); }
#pragma unroll
            for (int o = 16; o; o >>= 1) v += __shfl_xor_sync(~0u, v, o);
            mean_b = bf16r(mean);
            sd_b = bf16r(fsqrt(bf16r(bf16r(v * (1.f / kD)) + 1e-5f)));
        }
        if (warp < 5) {
            const int wi = min(tid, 143);
            uint4 sa, ca;
            do { sa = ld_word(&g_s.mod[b * 864 + wi]); ca = ld_word(&g_s.mod[b * 864 + 144 + wi]); }
            while (__any_sync(~0u, sa.z != tag || sa.w != tag || ca.z != tag || ca.w != tag) && --budget > 0);
            const float inv = frcp(sd_b);
            uint2 hv;
            hv.x = pack_bf16(ln_mod(bflo(x4.x), mean_b, inv, bf16r(1.f + bflo(ca.x)), bflo(sa.x)),
                             ln_mod(bfhi(x4.x), mean_b, inv, bf16r(1.f + bfhi(ca.x)), bfhi(sa.x)));
            hv.y = pack_bf16(ln_mod(bflo(x4.y), mean_b, inv, bf16r(1.f + bflo(ca.y)), bflo(sa.y)),
                             ln_mod(bfhi(x4.y), mean_b, inv, bf16r(1.f + bfhi(ca.y)), bfhi(sa.y)));
            if (tid < 144) *(uint2*)(smem + SM_H2 + tid * 8) = hv;
        }
        mbar_wait(bar(BAR_WQ), 0, budget); mbar_wait(bar(BAR_WQ + 1), 0, budget); mbar_wait(bar(BAR_WQ + 2), 0, budget);
        {
            const uint32_t base = sb + SM_W + ((lane >> 4) * 8 + (lane & 7)) * 128;
#pragma unroll
            for (int i = 0; i < 5; i++) {
#pragma unroll
                for (int mt = 0; mt < 4; mt++)
                    ldsm4t(wf[i][mt], base + (i < 4 ? warp + 8 * i : idx4) * 2048 + (((2 * mt + ((lane >> 3) & 1)) ^ (lane & 7)) << 4));
            }
        }
        bar_compute();
        {
            float c[4][4];
#pragma unroll
            for (int mt = 0; mt < 4; mt++) { c[mt][0] = c[mt][1] = c[mt][2] = c[mt][3] = 0.f; }
            const uint32_t* hp = (const uint32_t*)(smem + SM_H2) + t;
#pragma unroll
            for (int i = 0; i < 5; i++) {
                const int ks = i < 4 ? warp + 8 * i : idx4;
                const bool on = g == 0 && (i < 4 || five);
                const uint32_t b0 = on ? hp[ks * 8] : 0u, b1 = on ? hp[ks * 8 + 4] : 0u;
#pragma unroll
                for (int mt = 0; mt < 4; mt++) mma16(c[mt], wf[i][mt][0], wf[i][mt][1], wf[i][mt][2], wf[i][mt][3], b0, b1);
            }
            if (t == 0) {
#pragma unroll
                for (int mt = 0; mt < 4; mt++) { s_red[warp * 64 + mt * 16 + g] = c[mt][0]; s_red[warp * 64 + mt * 16 + 8 + g] = c[mt][2]; }
            }
        }
        bar_compute();
        if (warp == 0) {
            float2 s = *(const float2*)(s_red + lane * 2);
#pragma unroll
            for (int w = 1; w < 8; w++) { const float2 v = *(const float2*)(s_red + w * 64 + lane * 2); s.x += v.x; s.y += v.y; }
            const uint32_t qv = pack_bf16(s.x, s.y);
            const uint32_t off = SM_Q + (rank * 32 + lane) * 4;
            *(uint32_t*)(smem + off) = qv;
            st_async32(mapa(sb + off, rank ^ 1), qv, mapa(bar(BAR_Q), rank ^ 1));
            __syncwarp();
            if (lane == 0) mbar_arrive(bar(BAR_Q));
        }
        mbar_wait(bar(BAR_Q), 0, budget);
#pragma unroll
        for (int i = 0; i < 16; i++) qf[i] = *(const uint32_t*)(smem + SM_Q + ((i ^ g) * 4 + t) * 4);

#pragma unroll 1
        for (int pass = 0; pass < 3; pass++) {
            attend(pass == 0 ? 3 : pass == 1 ? (kSwitch - 6) / 2 : (kPairs - kSwitch) / 2, pass == 0 ? 6 : pass == 1 ? kSlots : 8);
            if (pass == 0) {
                slot = 2 * grp; par = 0;
                mbar_wait(bar(BAR_WO), 0, budget);
#pragma unroll
                for (int i = 0; i < 5; i++) {
#pragma unroll
                    for (int ks = 0; ks < 4; ks++) ldsm4t(wf[i][ks], sb + SM_W + ((lane >> 4) * 8 + ks * 16) * kWPitch + wtile(i));
                }
                __syncwarp();
                if (lane == 0) mbar_arrive(bar(BAR_WFREE));
                uint32_t k[5];
                const unsigned* const pk[5] = {&g_s.pick[b * 64 + warp * 8 + g], &g_s.pick[kCtas + (t >> 1) * 64 + warp * 8 + g],
                                               &g_s.pick[2 * kCtas + cta], &g_s.pick[cta], &g_s.pick[kCtas + cta]};
                const int wi = min(tid, 143);
                bool more;
                do {
                    more = false;
#pragma unroll
                    for (int i = 0; i < 5; i++) asm volatile("ld.relaxed.gpu.global.u32 %0, [%1];" : "=r"(k[i]) : "l"(pk[i]) : "memory");
                    if (warp < 5) {
                        uint4 u[8];
#pragma unroll
                        for (int j = 0; j < 8; j++) u[j] = ld_word(&g_s.mod[(j >> 2) * 864 + (2 + (j & 3)) * 144 + wi]);
#pragma unroll
                        for (int j = 0; j < 8; j++) {
                            more |= u[j].z != tag || u[j].w != tag;
                            *(uint2*)(smem + SM_TMP + (j * kD + wi * 4) * 2) = make_uint2(u[j].x, u[j].y);
                        }
                    }
#pragma unroll
                    for (int i = 0; i < 5; i++) more |= ((k[i] ^ tag << 1) >> 1) != 0;
                } while (__any_sync(~0u, more) && --budget > 0);
                p_in1 += (k[0] & 1) * 256; p_in3 += (k[1] & 1) * 256; p_xw += (k[2] & 1) * 256;
                mine = (k[3] & 1) | (k[4] & 1) << 1;
                bar_compute();
                {
                    const uint16_t* lq = (const uint16_t*)(smem + SM_TMP) + (tid >> 7) * 4 * kD + lcol;
                    const uint16_t* rq = (const uint16_t*)(smem + SM_TMP) + b * 3 * kD + rcol;
#pragma unroll
                    for (int i = 0; i < 5; i++) {
                        csb[i] = i < lcnt ? pack_bf16(1.f + bflo(lq[2 * kD + 128 * i]), bflo(lq[kD + 128 * i])) : 0u;
                        rgab[i] = i < rcnt ? rq[128 * i] | ((uint32_t)rq[3 * kD + 128 * i] << 16) : 0u;
                    }
                }
            }
            if (pass == 1) {
                if (t < 2) st_word(p_in1, 0, 0, 0, 0);
                st_word(p_in3, 0, 0, 0, 0);
                if (warp == 7 && lane < 2 * kX1Copies) st_word(p_x1, 0, 0, 0, 0);
                pin(p_in1); pin(p_in3); pin(p_xw); pin32(peer); pin32(a_comb); pin32(a_h2); pin32(rk);
            }
        }

        const uint32_t tag8 = tag % 255u + 1u;
        {
            float e[8], o[8];
#pragma unroll
            for (int j = 0; j < 8; j++) { e[j] = acc[j][0] + acc[j][3]; o[j] = acc[j][1] + acc[j][2]; }
#pragma unroll
            for (int j = 0; j < 8; j += 2) { e[j] += __shfl_xor_sync(~0u, e[j + 1], 1); o[j] += __shfl_xor_sync(~0u, o[j + 1], 1); }
#pragma unroll
            for (int j = 0; j < 8; j += 4) { e[j] += __shfl_xor_sync(~0u, e[j + 2], 2); o[j] += __shfl_xor_sync(~0u, o[j + 2], 2); }
            const uint32_t o_comb = SM_COMB + (warp * 66 + lane * 2) * 4, o_cm = SM_CM + lane * 64 + warp * 4;
            const uint32_t rbar = peer + SM_BAR + BAR_COMB * 8;
            st_async64(peer + o_comb + 8 * 66 * 4, __float_as_uint(rk ? e[0] : e[4]), __float_as_uint(rk ? o[0] : o[4]), rbar);
            if (lane < 2) st_async32(peer + o_cm + 8 * 4, __float_as_uint(lane ? l : m), rbar);
            stsf2(sb + o_comb, rk ? e[4] : e[0], rk ? o[4] : o[0]);
            if (lane < 2) sts32(sb + o_cm, __float_as_uint(lane ? l : m));
            __syncwarp();
            if (lane == 0) mbar_arrive(bar(BAR_COMB));
            mbar_wait(bar(BAR_COMB), 0, budget);
            const float4 m0 = ldsf4(sb + SM_CM), m1 = ldsf4(sb + SM_CM + 16), m2 = ldsf4(sb + SM_CM + 32), m3 = ldsf4(sb + SM_CM + 48);
            const float4 mq = ldsf4(sb + SM_CM + t * 16), lq = ldsf4(sb + SM_CL + t * 16);
            const float o0 = ldsf(a_comb), o1 = ldsf(a_comb + 66 * 4), o2 = ldsf(a_comb + 132 * 4), o3 = ldsf(a_comb + 198 * 4);
            const int f = tid >> 2;
            uint32_t a_ob = sb + SM_OB + ((f >> 4) * 16 + (f & 7) * 2 + ((f >> 3) & 1)) * 2;
            pin32(a_ob);
            const float M = kL2E * fmaxf(fmaxf(fmaxf(fmaxf(m0.x, m0.y), fmaxf(m0.z, m0.w)), fmaxf(fmaxf(m1.x, m1.y), fmaxf(m1.z, m1.w))),
                                         fmaxf(fmaxf(fmaxf(m2.x, m2.y), fmaxf(m2.z, m2.w)), fmaxf(fmaxf(m3.x, m3.y), fmaxf(m3.z, m3.w))));
            const float f0 = ex2(fmaf(mq.x, kL2E, -M)), f1 = ex2(fmaf(mq.y, kL2E, -M)), f2 = ex2(fmaf(mq.z, kL2E, -M)), f3 = ex2(fmaf(mq.w, kL2E, -M));
            float ov = (f0 * o0 + f1 * o1) + (f2 * o2 + f3 * o3);
            float L = (f0 * lq.x + f1 * lq.y) + (f2 * lq.z + f3 * lq.w);
            ov += __shfl_xor_sync(~0u, ov, 1); L += __shfl_xor_sync(~0u, L, 1);
            ov += __shfl_xor_sync(~0u, ov, 2); L += __shfl_xor_sync(~0u, L, 2);
            const uint16_t ob = bf16bits(ov * frcp(L));
            if (t == 0) sts16(a_ob, ob);
            bar_compute();
        }
        {
            const uint4 ob0 = lds128(sb + SM_OB + t * 32), ob1 = lds128(sb + SM_OB + t * 32 + 16);
            float v[5];
#pragma unroll
            for (int i = 0; i < 5; i++) {
                float c[4] = {0.f, 0.f, 0.f, 0.f};
                mma16(c, wf[i][0][0], wf[i][0][1], wf[i][0][2], wf[i][0][3], ob0.x, ob0.y);
                mma16(c, wf[i][1][0], wf[i][1][1], wf[i][1][2], wf[i][1][3], ob0.z, ob0.w);
                mma16(c, wf[i][2][0], wf[i][2][1], wf[i][2][2], wf[i][2][3], ob1.x, ob1.y);
                mma16(c, wf[i][3][0], wf[i][3][1], wf[i][3][2], wf[i][3][3], ob1.z, ob1.w);
                v[i] = (t & 1) ? c[2] : c[0];
            }
            if (t < 2) put_f24x5<true>(p_in1, v, tag8);
        }
        uint32_t w1f[5][2][4], w1h[5][2], w2f[5][2][4], w2h[5][2];
#pragma unroll
        for (int u = 0; u < 4; u++) { w1f[4][0][u] = w1f[4][1][u] = w2f[4][0][u] = w2f[4][1][u] = 0; }
        w1h[4][0] = w1h[4][1] = w2h[4][0] = w2h[4][1] = 0;
        auto ff_ready = [&](uint32_t n) { return __any_sync(~0u, lds32(sb + SM_FLAG) >= n) != 0; };
        auto load_w1 = [&]() {
            const uint32_t l4 = sb + SM_W1 + ((lane >> 4) * 8 + (lane & 7)) * kW1Pitch + ((lane >> 3) & 1) * 16;
            const uint32_t l2 = sb + SM_W1 + (lane & 15) * kW1Pitch + 64;
#pragma unroll
            for (int i = 0; i < 5; i++) {
                const uint32_t ro = (i < 4 ? warp + 8 * i : idx4) * 16 * kW1Pitch;
                if (i < 4 || five) { ldsm4t(w1f[i][0], l4 + ro); ldsm4t(w1f[i][1], l4 + ro + 32); ldsm2t(w1h[i], l2 + ro); }
            }
        };
        auto load_w2 = [&](bool wait) {
#pragma unroll
            for (int ks = 0; ks < 3; ks++) {
                if (wait) while (!ff_ready(ks < 2 ? 8 + 2 * ks : 11) && --budget > 0) {}
#pragma unroll
                for (int i = 0; i < 5; i++) {
                    const uint32_t a2 = sb + SM_W2 + wtile(i), a4 = a2 + (lane >> 4) * 8 * kWPitch;
                    if (i < 4 || five) {
                        if (ks < 2) ldsm4t(w2f[i][ks], a4 + ks * 16 * kWPitch); else ldsm2t(w2h[i], a2 + 32 * kWPitch);
                    }
                }
            }
        };
        float x1[5] = {0.f, 0.f, 0.f, 0.f, 0.f};
        if (warp == 7) {
            float s[5];
            pin(p_x1);
            uint4* const p_g1 = &g_s.in1[cta * 512 + (mine & 1) * 256 + lane];
            gather_sum<4>(p_g1, tag8, s, budget);
            sts32(sb + SM_FLAG + 4, 1);
#pragma unroll
            for (int i = 0; i < 5; i++) x1[i] = bf16r(rx[i] + bf16r(bflo(rgab[i]) * bf16r(s[i])));
            if (lane < 2 * kX1Copies) xchg_word(p_x1, pack_bf16(x1[1], x1[2]), pack_bf16(x1[3], x1[4]), tag, __float_as_uint(x1[0]) | tag8);
#pragma unroll
            for (int k = 0; k < 4; k++) st_word(p_g1 + k * 32, 0, 0, 0, 0);
        }
        bool have1 = false, have2 = false;
        while (true) {
            if (!have1 && ff_ready(6)) { load_w1(); have1 = true; }
            if (!have2 && ff_ready(11)) { load_w2(false); have2 = true; }
            if (__any_sync(~0u, lds32(sb + SM_FLAG + 4)) || --budget <= 0) break;
        }
        {
            uint4 w;
            uint32_t w0;
            while (true) {
                w = ld_word(p_xw);
                asm volatile("ld.relaxed.gpu.global.u32 %0, [%1];" : "=r"(w0) : "l"(&p_xw[-(tid & 127)].w) : "memory");
                if (!have1 && ff_ready(6)) { load_w1(); have1 = true; }
                else if (have1 && !have2 && ff_ready(11)) { load_w2(false); have2 = true; }
                if (!__any_sync(~0u, w.z != tag || (w0 & 0xffffu) != tag8) || --budget <= 0) break;
            }
            const float xv[5] = {bfhi(w.w), bflo(w.x), bfhi(w.x), bflo(w.y), bfhi(w.y)};
            const float shift = bfhi(w0);
            float s1 = 0.f, s2 = 0.f;
#pragma unroll
            for (int i = 0; i < 5; i++) { const float d = i < lcnt ? xv[i] - shift : 0.f; s1 += d; s2 = fmaf(d, d, s2); }
#pragma unroll
            for (int o = 16; o; o >>= 1) { s1 += __shfl_xor_sync(~0u, s1, o); s2 += __shfl_xor_sync(~0u, s2, o); }
            if (lane == 0) stsf2(sb + SM_LN + warp * 8, s1, s2);
            bar_compute();
            const float4 a0 = ldsf4(sb + SM_LN + grp * 32), a1 = ldsf4(sb + SM_LN + grp * 32 + 16);
            const float md = ((a0.x + a0.z) + (a1.x + a1.z)) * (1.f / kD);
            const float var = fmaxf(fmaf(-md, md, ((a0.y + a0.w) + (a1.y + a1.w)) * (1.f / kD)), 0.f);
            const float mb = bf16r(shift + md), inv = frcp(bf16r(fsqrt(bf16r(bf16r(var) + 1e-5f))));
#pragma unroll
            for (int i = 0; i < 5; i++) {
                const uint16_t hv = bf16bits(ln_mod(xv[i], mb, inv, bflo(csb[i]), bfhi(csb[i])));
                if (i < lcnt) sts16(a_h2 + i * 256, hv);
            }
            if (!have1) { while (!ff_ready(6) && --budget > 0) {} load_w1(); }
            bar_compute();
        }
        {
            float c[3][4];
#pragma unroll
            for (int u = 0; u < 3; u++) { c[u][0] = c[u][1] = c[u][2] = c[u][3] = 0.f; }
            const uint32_t hp = sb + SM_H2 + ((g & 1) * kHPitch + t * 4) * 2;
            uint2 hb[5];
#pragma unroll
            for (int i = 0; i < 5; i++) hb[i] = lds64(hp + (i < 4 ? warp + 8 * i : idx4) * 32);
            if (!five) hb[4] = make_uint2(0, 0);
#pragma unroll
            for (int i = 0; i < 5; i++) {
                mma16(c[0], w1f[i][0][0], w1f[i][0][1], w1f[i][0][2], w1f[i][0][3], hb[i].x, hb[i].y);
                mma16(c[1], w1f[i][1][0], w1f[i][1][1], w1f[i][1][2], w1f[i][1][3], hb[i].x, hb[i].y);
                mma16(c[2], w1h[i][0], 0u, w1h[i][1], 0u, hb[i].x, hb[i].y);
            }
            if (t == 0) {
                const uint32_t rp = sb + SM_RED + (warp * 40 + g) * 8;
                stsf2(rp, c[0][0], c[0][1]);       stsf2(rp + 64, c[0][2], c[0][3]);
                stsf2(rp + 128, c[1][0], c[1][1]); stsf2(rp + 192, c[1][2], c[1][3]);
                stsf2(rp + 256, c[2][0], c[2][1]);
            }
            bar_compute();
            if (tid < 80) {
                const uint32_t rp = sb + SM_RED + tid * 4;
                const float r0 = ldsf(rp), r1 = ldsf(rp + 320), r2 = ldsf(rp + 640), r3 = ldsf(rp + 960);
                const float r4 = ldsf(rp + 1280), r5 = ldsf(rp + 1600), r6 = ldsf(rp + 1920), r7 = ldsf(rp + 2240);
                float s = ((r0 + r1) + (r2 + r3)) + ((r4 + r5) + (r6 + r7));
                s = s < 0.f ? 0.f : s;
                const int k = tid >> 1;
                sts16(sb + SM_H1 + ((tid & 1) * 48 + (k & ~15) + ((k >> 1) & 3) * 4 + ((k >> 3) & 1) * 2 + (k & 1)) * 2, bf16bits(s));
            }
            if (!have2) load_w2(true);
            bar_compute();
        }
        {
            const uint32_t hp = sb + SM_H1 + ((g & 1) * 48 + t * 4) * 2;
            const uint2 h0 = lds64(hp), h1 = lds64(hp + 32);
            const uint32_t h2 = lds32(hp + 64);
            float v[5];
#pragma unroll
            for (int i = 0; i < 5; i++) {
                float c[4] = {0.f, 0.f, 0.f, 0.f};
                mma16(c, w2f[i][0][0], w2f[i][0][1], w2f[i][0][2], w2f[i][0][3], h0.x, h0.y);
                mma16(c, w2f[i][1][0], w2f[i][1][1], w2f[i][1][2], w2f[i][1][3], h1.x, h1.y);
                mma8(c, rk ? 0u : w2h[i][0], rk ? 0u : w2h[i][1], h2);
                v[i] = (t & 1) ? ((t & 2) ? c[3] : c[2]) : ((t & 2) ? c[1] : c[0]);
            }
            put_f24x5<false>(p_in3, v, tag8);
        }
        if (warp == 7) {
            uint16_t* p_out = (uint16_t*)p.out + rcol;
            uint4* p_g3 = &g_s.in3[cta * 512 + (mine & 2) * 128 + lane];
            pin(p_out); pin(p_g3);
            { const unsigned c0 = (unsigned)clock(); while ((unsigned)clock() - c0 < kLastPollDelay) {} }
            float s[5];
            gather_sum<8>(p_g3, tag8, s, budget);
            if (lane < 2) {
#pragma unroll
                for (int i = 0; i < 5; i++) {
                    const uint16_t ov = bf16bits(x1[i] + bf16r(bfhi(rgab[i]) * bf16r(s[i])));
                    if (i < rcnt) p_out[128 * i] = ov;
                }
                if (cta == 0 && lane == 0) asm volatile("st.relaxed.gpu.global.u32 [%0], %1;" :: "l"(&g_s.epoch), "r"(tag) : "memory");
            }
        }
        return;
    }
    {
        asm volatile("setmaxnreg.dec.sync.aligned.u32 40;");
        if (warp > 8) {
            asm volatile("barrier.cluster.arrive.relaxed.aligned;" ::: "memory");
            const uint32_t start = (uint32_t)clock();
            while ((uint32_t)clock() - start < kProbeDelay) {}
            if (lane == 0) {
                uint4* const q = warp == 9 ? &g_s.in1[cta * 512 + (cta & 63) * 2] : warp == 10 ? &g_s.in3[cta * 512 + cta * 2]
                                                                                              : &g_s.x1[(cta & (kX1Copies - 2)) * 256 + cta * 2];
                st_word(q, 0, 0, 0, 0); st_word(q + 1, 0, 0, 0, 0); st_word(q + 256, 0, 0, 0, 0); st_word(q + 257, 0, 0, 0, 0);
                uint32_t tag;
                asm volatile("ld.relaxed.gpu.global.u32 %0, [%1];" : "=r"(tag) : "l"(&g_s.epoch) : "memory");
                uint32_t best[2] = {~0u, ~0u};
#pragma unroll 1
                for (int r = 0; r < 2 * kProbes; r++) {
                    uint32_t v;
                    const uint32_t c0 = (uint32_t)clock();
                    asm volatile("atom.relaxed.gpu.global.exch.b32 %0, [%1], 0;" : "=r"(v) : "l"(q + (r & 1) * 256) : "memory");
                    asm volatile("bar.warp.sync %0;" :: "r"(v | 1u) : "memory");
                    const uint32_t dt = (uint32_t)clock() - c0;
                    if (r & 1) best[1] = min(best[1], dt); else best[0] = min(best[0], dt);
                    if ((r & 1) && r > 1 && c0 - start > kProbeLimit) break;
                }
                const uint32_t pick = (tag + 1) << 1 | (best[1] < best[0]);
                asm volatile("st.relaxed.gpu.global.u32 [%0], %1;" :: "l"(&g_s.pick[(warp - 9) * kCtas + cta]), "r"(pick) : "memory");
            }
            __syncwarp();
            asm volatile("barrier.cluster.wait.acquire.aligned;" ::: "memory");
            return;
        }
        const char* kbase = (const char*)p.k + ((size_t)cl * kSk + (size_t)rank * 128) * (kDh * 2);
        const char* vbase = (const char*)p.v + ((size_t)cl * kSk + (size_t)rank * 128) * (kDh * 2);
        uint64_t pol;
        asm volatile("createpolicy.fractional.L2::evict_first.b64 %0, 1.0;" : "=l"(pol));
        auto issue = [&](int i, int slot) {
            const uint32_t fb = bar(BAR_FULL + slot);
            const char* src = ((i & 1) ? vbase : kbase) + (size_t)((i >> 2) * 4 + ((i >> 1) & 1)) * kTileBytes;
            mbar_expect_tx(fb, kTileBytes);
            bulk_load(sb + SM_RING + slot * kTileBytes, src, kTileBytes, fb, pol);
        };
        auto issue_wq = [&](int s) {
            mbar_expect_tx(bar(BAR_WQ + s), 192 * 128);
            tma_load_2d(sb + SM_W + s * 192 * 128, &wqmap, h * 128 + rank * 64, s * 192, bar(BAR_WQ + s));
        };
        if (lane == 0) {
            mbar_init(bar(BAR_M), 1); mbar_init(bar(BAR_WQ), 1);
            asm volatile("fence.proxy.async.shared::cta;" ::: "memory");
            if (do_mod) {
                mbar_expect_tx(bar(BAR_M), 576 * 64);
                for (int s = 0; s < 3; s++) tma_load_2d(sb + SM_M + s * 192 * 64, &wmmap, cta * 32, s * 192, bar(BAR_M));
            }
            issue_wq(0);
#pragma unroll
            for (int i = 0; i < BAR_COUNT; i++)
                if (i != BAR_M && i != BAR_WQ)
                    mbar_init(bar(i), i >= BAR_EMPTY && i < BAR_WO ? 4 : i == BAR_WFREE ? 8 : i == BAR_Q ? 2 : i == BAR_COMB ? 9 : 1);
            sts32(sb + SM_FLAG, 0); sts32(sb + SM_FLAG + 4, 0);
            mbar_expect_tx(bar(BAR_Q), 128);
            mbar_expect_tx(bar(BAR_COMB), 8 * (256 + 8));
            asm volatile("fence.mbarrier_init.release.cluster;" ::: "memory");
        }
        __syncwarp();
        asm volatile("barrier.cluster.arrive.relaxed.aligned;" ::: "memory");
        if (lane == 0) {
            asm volatile("fence.proxy.async.shared::cta;" ::: "memory");
            asm volatile("prefetch.tensormap [%0];" :: "l"(&womap) : "memory");
            asm volatile("prefetch.tensormap [%0];" :: "l"(&w1map) : "memory");
            asm volatile("prefetch.tensormap [%0];" :: "l"(&w2map) : "memory");
        }
        __syncwarp();
        asm volatile("barrier.cluster.wait.acquire.aligned;" ::: "memory");
        if (lane == 0) {
            unsigned epoch;
            asm volatile("ld.relaxed.gpu.global.u32 %0, [%1];" : "=r"(epoch) : "l"(&g_s.epoch) : "memory");
            if (do_mod) mbar_wait(bar(BAR_M), 0, budget);
            issue_wq(1);
            mbar_wait(bar(BAR_WQ), 0, budget);
            issue_wq(2);
            mbar_wait(bar(BAR_WQ + 1), 0, budget);
            issue(0, 0); issue(1, 1);
            mbar_wait(bar(BAR_WQ + 2), 0, budget);
            issue(2, 2);
            for (int i = 3; i < 6; i++) { mbar_wait(bar(BAR_FULL + i - 3), 0, budget); issue(i, i); }
            mbar_wait(bar(BAR_Q), 0, budget);
            mbar_expect_tx(bar(BAR_WO), 64 * kWPitch);
            tma_load_rows(sb + SM_W, &womap, h * 128 + rank * 64, bar(BAR_WO));
            for (int i = 3; i < 6; i++) mbar_wait(bar(BAR_FULL + i), 0, budget);
            for (int i = 6; i < 12; i++) { mbar_wait(bar(BAR_EMPTY + i - 6), 0, budget); issue(i, i - 6); }
            auto issue_ff = [&](int c) {
                const uint32_t fb = bar(BAR_FF + c);
                if (c < 6) {
                    mbar_expect_tx(fb, 96 * kW1Pitch);
                    tma_load_2d(sb + SM_W1 + c * 96 * kW1Pitch, &w1map, ffcol0, c * 96, fb);
                } else {
                    const bool mine = c < 10 || rank == 0;
                    mbar_expect_tx(fb, mine ? 8 * kWPitch : 0);
                    if (mine) tma_load_rows(sb + SM_W2 + (c - 6) * 8 * kWPitch, &w2map, ffcol0 + (c - 6) * 8, fb);
                }
            };
            unsigned* const progress = &g_s.progress[(epoch & 1) * 32];
            if (cta == 0) asm volatile("st.relaxed.gpu.global.u32 [%0], 0;" :: "l"(&g_s.progress[(~epoch & 1) * 32]) : "memory");
            int prog = 0, trim = 0, frac = 0;
            int reported = 12, landed = 12, lslot = 0, slot = 0, window = kWinMid;
            uint32_t lpar = 0, par = 1;
            for (int i = 12; i < 2 * kPairs; i++) {
                if (i == 18) mbar_wait(bar(BAR_WFREE), 0, budget);
                if (i == 2 * kSwitch + 8)
                    for (int s = 8; s < 12; s++) mbar_wait(bar(BAR_EMPTY + s), par ^ 1, budget);
                if (!(i & 1)) {
                    const int lead = (landed - 12) * kCtas - prog - kWinBias;
                    asm volatile("red.relaxed.gpu.global.add.u32 [%0], %1;" :: "l"(progress), "r"(landed - reported) : "memory");
                    reported = landed;
                    trim = min(max(trim + (lead > kTrimFrom ? (lead - kTrimFrom) >> kTrimShift : -kTrimDecay), 0), kTrimMax);
                    const int w128 = min(max(kWinMid - (lead >> 7), kWinMin), i < 2 * kSwitch ? kWinMax : 8) * 128 - trim;
                    frac = (frac & 127) + (w128 & 127);
                    window = min((w128 >> 7) + (frac >> 7), i < 2 * kSwitch ? kWinMax : 8);
                    if (lead > kFarAhead * kCtas) window = 1;
                    asm volatile("ld.relaxed.gpu.global.u32 %0, [%1];" : "=r"(prog) : "l"(progress) : "memory");
                }
                while (i - landed >= window) {
                    mbar_wait(bar(BAR_FULL + lslot), lpar, budget);
                    if (++lslot == (landed < 2 * kSwitch ? kSlots : 8)) { lslot = 0; lpar ^= 1; }
                    landed++;
                }
                mbar_wait(bar(BAR_EMPTY + slot), par, budget);
                issue(i, slot);
                if (++slot == (i < 2 * kSwitch ? kSlots : 8)) { slot = 0; par ^= 1; }
            }
            asm volatile("red.relaxed.gpu.global.add.u32 [%0], %1;" :: "l"(progress), "r"(2 * kPairs - reported) : "memory");
            const int ffwin = prog >= kTotal - kFfLate ? kFfWinLate : kFfWin;
            while (prog < kTotal - kFfHold && --budget > 0)
                asm volatile("ld.relaxed.gpu.global.u32 %0, [%1];" : "=r"(prog) : "l"(progress) : "memory");
            int lc = 0;
            auto piece_landed = [&]() {
                mbar_wait(bar(BAR_FF + lc), 0, budget);
                sts32(sb + SM_FLAG, ++lc);
            };
            int flight = 2 * (2 * kPairs - landed);
            for (int c = 0; c < 11; c++) {
                while (flight >= ffwin) {
                    if (landed < 2 * kPairs) {
                        mbar_wait(bar(BAR_FULL + lslot), lpar, budget);
                        if (++lslot == 8) { lslot = 0; lpar ^= 1; }
                        landed++; flight -= 2;
                    } else {
                        piece_landed(); flight--;
                    }
                }
                issue_ff(c);
                flight++;
            }
            while (lc < 11) piece_landed();
        }
    }
}

typedef CUresult (*EncodeTiledFn)(CUtensorMap*, CUtensorMapDataType, cuuint32_t, void*, const cuuint64_t*,
                                  const cuuint64_t*, const cuuint32_t*, const cuuint32_t*, CUtensorMapInterleave,
                                  CUtensorMapSwizzle, CUtensorMapL2promotion, CUtensorMapFloatOOBfill);

}

extern "C" void kernel_launch(void* const* d_in, const int* in_sizes, int n_in, void* d_out, int out_size) {
    (void)in_sizes; (void)n_in; (void)out_size;
    static EncodeTiledFn encode = nullptr;
    if (!encode) {
        void* fn = nullptr;
        cudaDriverEntryPointQueryResult qr;
        cudaGetDriverEntryPoint("cuTensorMapEncodeTiled", &fn, cudaEnableDefault, &qr);
        encode = (EncodeTiledFn)fn;
        cudaFuncSetAttribute(fused_decode_kernel, cudaFuncAttributeMaxDynamicSharedMemorySize, SM_TOTAL);
    }
    Params p;
    p.x = (const __nv_bfloat16*)d_in[0];
    p.k = (const __nv_bfloat16*)d_in[1];
    p.v = (const __nv_bfloat16*)d_in[2];
    p.c = (const __nv_bfloat16*)d_in[8];
    p.out = (__nv_bfloat16*)d_out;
    CUtensorMap w1map;
    const cuuint64_t dims[2] = {(cuuint64_t)kDff, (cuuint64_t)kD};
    const cuuint64_t strides[1] = {(cuuint64_t)kDff * 2};
    const cuuint32_t box[2] = {40, 96};
    const cuuint32_t estr[2] = {1, 1};
    encode(&w1map, CU_TENSOR_MAP_DATA_TYPE_BFLOAT16, 2, d_in[6], dims, strides, box, estr,
           CU_TENSOR_MAP_INTERLEAVE_NONE, CU_TENSOR_MAP_SWIZZLE_NONE, CU_TENSOR_MAP_L2_PROMOTION_L2_128B,
           CU_TENSOR_MAP_FLOAT_OOB_FILL_NONE);
    CUtensorMap wqmap;
    const cuuint64_t qdims[2] = {(cuuint64_t)kHD, (cuuint64_t)kD};
    const cuuint64_t qstrides[1] = {(cuuint64_t)kHD * 2};
    const cuuint32_t qbox[2] = {64, 192};
    encode(&wqmap, CU_TENSOR_MAP_DATA_TYPE_BFLOAT16, 2, d_in[3], qdims, qstrides, qbox, estr,
           CU_TENSOR_MAP_INTERLEAVE_NONE, CU_TENSOR_MAP_SWIZZLE_128B, CU_TENSOR_MAP_L2_PROMOTION_NONE,
           CU_TENSOR_MAP_FLOAT_OOB_FILL_NONE);
    CUtensorMap wmmap;
    const cuuint64_t mdims[2] = {(cuuint64_t)kMod, (cuuint64_t)kD};
    const cuuint64_t mstrides[1] = {(cuuint64_t)kMod * 2};
    const cuuint32_t mbox[2] = {32, 192};
    encode(&wmmap, CU_TENSOR_MAP_DATA_TYPE_BFLOAT16, 2, d_in[9], mdims, mstrides, mbox, estr,
           CU_TENSOR_MAP_INTERLEAVE_NONE, CU_TENSOR_MAP_SWIZZLE_64B, CU_TENSOR_MAP_L2_PROMOTION_NONE,
           CU_TENSOR_MAP_FLOAT_OOB_FILL_NONE);
    CUtensorMap womap, w2map;
    const cuuint64_t odims[3] = {64, 9, (cuuint64_t)kHD}, fdims[3] = {64, 9, (cuuint64_t)kDff};
    const cuuint64_t rstrides[2] = {128, (cuuint64_t)kWPitch};
    const cuuint32_t obox[3] = {64, 9, 64}, fbox[3] = {64, 9, 8}, estr3[3] = {1, 1, 1};
    encode(&womap, CU_TENSOR_MAP_DATA_TYPE_BFLOAT16, 3, d_in[4], odims, rstrides, obox, estr3,
           CU_TENSOR_MAP_INTERLEAVE_NONE, CU_TENSOR_MAP_SWIZZLE_128B, CU_TENSOR_MAP_L2_PROMOTION_NONE,
           CU_TENSOR_MAP_FLOAT_OOB_FILL_NONE);
    encode(&w2map, CU_TENSOR_MAP_DATA_TYPE_BFLOAT16, 3, d_in[7], fdims, rstrides, fbox, estr3,
           CU_TENSOR_MAP_INTERLEAVE_NONE, CU_TENSOR_MAP_SWIZZLE_128B, CU_TENSOR_MAP_L2_PROMOTION_NONE,
           CU_TENSOR_MAP_FLOAT_OOB_FILL_NONE);
    fused_decode_kernel<<<kCtas, kThreads, SM_TOTAL>>>(wmmap, wqmap, womap, w1map, w2map, p);
}
```
